```python
import torch

def _softmax(x, axis=-1):
    return torch.softmax(x, dim=axis)
def _gelu(x):
    return torch.nn.functional.gelu(x, approximate="tanh")
def _silu(x):
    return torch.nn.functional.silu(x)
def _sigmoid(x):
    return torch.sigmoid(x)
def _layernorm(x, axis=-1, eps=1e-5):
    m = x.mean(dim=axis, keepdim=True)
    v = x.var(dim=axis, keepdim=True, unbiased=False)
    return (x - m) / torch.sqrt(v + eps)
def _scatter_add(tgt, idx, src, axis=0):
    return tgt.clone().index_add_(axis, idx, src)
def _segment_sum(src, seg, n):
    out = torch.zeros((n,) + src.shape[1:], dtype=src.dtype)
    return out.index_add_(0, seg, src)
def _pad(x, pw):
    flat = tuple(v for pair in reversed(pw) for v in pair)
    return torch.nn.functional.pad(x, flat)

kernel_name = 'standalone__instancenorm__prompt'

def setup_inputs():

    _w = (lambda a: (lambda t: t.to(torch.bfloat16) if t.is_floating_point() else t)(torch.as_tensor(a)))
    B, C, H, W = 1, 640, 2048, 32
    return {
        "x": _w(abs((lambda *s: torch.randn(*s, dtype=torch.bfloat16) * 0.05)(B, C, H, W))),
        "g": _w((lambda *s: torch.randn(*s, dtype=torch.bfloat16) * 0.05)(C) + 1.0),
        "b": _w((lambda *s: torch.randn(*s, dtype=torch.bfloat16) * 0.4)(C)),
    }

def reference(x, g, b):
    mu = x.mean(axis=(-2, -1), keepdims=True)
    var = ((x - mu) ** 2).mean(axis=(-2, -1), keepdims=True)
    xhat = (x - mu) / torch.sqrt(var + 1e-5)
    return xhat * g.reshape(1, -1, 1, 1) + b.reshape(1, -1, 1, 1)
```

```cpp
#include <cuda_runtime.h>
#include <cuda_bf16.h>
#include <stdint.h>
#include <string.h>

namespace {

constexpr int CHB = 16384;
constexpr int NS = 14;
constexpr int UPC = 8;
constexpr int NCONS = 512;
constexpr int MAXU = 40;
constexpr int GRID = 128;
constexpr int SMEM = NS * CHB + NS * 16 + 512;

struct Sched {
    signed char pace[MAXU];
    signed char need[MAXU];
    unsigned char pf[MAXU + 1];
    int pf_start;
    int F;
    unsigned short tw[MAXU];
};

__device__ __forceinline__ uint32_t smem_u32(const void* p) { return (uint32_t)__cvta_generic_to_shared(p); }
__device__ __forceinline__ void mbar_init(uint32_t bar, uint32_t cnt) { asm volatile("mbarrier.init.shared::cta.b64 [%0], %1;" :: "r"(bar), "r"(cnt) : "memory"); }
__device__ __forceinline__ void mbar_expect_tx(uint32_t bar, uint32_t bytes) { asm volatile("mbarrier.arrive.expect_tx.shared::cta.b64 _, [%0], %1;" :: "r"(bar), "r"(bytes) : "memory"); }
__device__ __forceinline__ void mbar_arrive(uint32_t bar) { asm volatile("mbarrier.arrive.shared::cta.b64 _, [%0];" :: "r"(bar) : "memory"); }
__device__ __forceinline__ bool mbar_try(uint32_t bar, uint32_t parity) {
    uint32_t ok;
    asm volatile("{\n.reg .pred p;\nmbarrier.try_wait.parity.shared::cta.b64 p, [%1], %2;\nselp.u32 %0, 1, 0, p;\n}" : "=r"(ok) : "r"(bar), "r"(parity) : "memory");
    return ok;
}
__device__ __forceinline__ void mbar_wait(uint32_t bar, uint32_t parity) {
    int it = 0;
    while (!mbar_try(bar, parity)) { if (++it > (1 << 22)) __trap(); }
}
__device__ __forceinline__ void bulk_load(uint32_t dst, const void* src, uint32_t bytes, uint32_t bar, uint64_t pol) {
    asm volatile("cp.async.bulk.shared::cluster.global.mbarrier::complete_tx::bytes.L2::cache_hint [%0], [%1], %2, [%3], %4;"
                 :: "r"(dst), "l"(src), "r"(bytes), "r"(bar), "l"(pol) : "memory");
}
__device__ __forceinline__ void bulk_prefetch(const void* src, uint32_t bytes) {
    asm volatile("cp.async.bulk.prefetch.L2.global [%0], %1;" :: "l"(src), "r"(bytes) : "memory");
}
__device__ __forceinline__ uint64_t pol_ef() { uint64_t p; asm volatile("createpolicy.fractional.L2::evict_first.b64 %0, 1.0;" : "=l"(p)); return p; }
__device__ __forceinline__ uint4 lds128(uint32_t a) {
    uint4 v; asm volatile("ld.shared.v4.u32 {%0,%1,%2,%3}, [%4];" : "=r"(v.x), "=r"(v.y), "=r"(v.z), "=r"(v.w) : "r"(a) : "memory"); return v;
}
__device__ __forceinline__ void st_pol(void* p, uint4 v, uint64_t pol) {
    asm volatile("st.global.L2::cache_hint.v4.u32 [%0], {%1,%2,%3,%4}, %5;" :: "l"(p), "r"(v.x), "r"(v.y), "r"(v.z), "r"(v.w), "l"(pol) : "memory");
}
__device__ __forceinline__ uint32_t gtime32() { uint32_t t; asm volatile("mov.u32 %0, %globaltimer_lo;" : "=r"(t)); return t; }
__device__ __forceinline__ float bf_lo(uint32_t u) { return __uint_as_float(u << 16); }
__device__ __forceinline__ float bf_hi(uint32_t u) { return __uint_as_float(u & 0xffff0000u); }
__device__ __forceinline__ uint32_t pack_bf(float lo, float hi) { uint32_t r; asm("cvt.rn.bf16x2.f32 %0, %1, %2;" : "=r"(r) : "f"(hi), "f"(lo)); return r; }
__device__ __forceinline__ void acc4(uint4 v, float K, float& s0, float& s1, float& q0, float& q1) {
    uint32_t w[4] = {v.x, v.y, v.z, v.w};
#pragma unroll
    for (int i = 0; i < 4; i++) {
        float a = bf_lo(w[i]) - K, b = bf_hi(w[i]) - K;
        s0 += a; s1 += b; q0 = fmaf(a, a, q0); q1 = fmaf(b, b, q1);
    }
}
__device__ __forceinline__ uint4 norm4(uint4 v, float A, float B) {
    uint4 o;
    o.x = pack_bf(fmaf(bf_lo(v.x), A, B), fmaf(bf_hi(v.x), A, B));
    o.y = pack_bf(fmaf(bf_lo(v.y), A, B), fmaf(bf_hi(v.y), A, B));
    o.z = pack_bf(fmaf(bf_lo(v.z), A, B), fmaf(bf_hi(v.z), A, B));
    o.w = pack_bf(fmaf(bf_lo(v.w), A, B), fmaf(bf_hi(v.w), A, B));
    return o;
}

__global__ void __launch_bounds__(NCONS + 32, 1)
instnorm_kernel(const char* __restrict__ x, const __nv_bfloat16* __restrict__ g, const __nv_bfloat16* __restrict__ b,
                char* __restrict__ y, int nchan, const __grid_constant__ Sched sc) {
    extern __shared__ __align__(128) char smem[];
    uint32_t ring = smem_u32(smem);
    uint32_t full = ring + NS * CHB, empty = full + NS * 8;
    float* red = (float*)(smem + NS * CHB + NS * 16);
    float* gb = red + 64;
    const int tid = threadIdx.x;
    const int nch = (nchan - blockIdx.x + gridDim.x - 1) / gridDim.x;
    const int nu = nch * UPC;
    const uint32_t tstart = gtime32();
    const uint64_t pol = pol_ef();
    if (tid == NCONS) {
        for (int s = 0; s < NS; s++) { mbar_init(full + s * 8, 1); mbar_init(empty + s * 8, NCONS / 32); }
        asm volatile("fence.mbarrier_init.release.cluster;" ::: "memory");
        asm volatile("fence.proxy.async.shared::cta;" ::: "memory");
        for (int u = 0; u < sc.F; u++) {
            size_t off = (size_t)(blockIdx.x + (u >> 3) * gridDim.x) * (UPC * CHB) + (u & 7) * CHB;
            mbar_expect_tx(full + u * 8, CHB);
            bulk_load(ring + u * CHB, x + off, CHB, full + u * 8, pol);
        }
    }
    __syncthreads();
    if (tid >= NCONS) {
        if (tid == NCONS) {
            int rel = 0, rs = 0, rp = 0;
            int arr = 0, as = 0, ap = 0;
            int s = sc.F % NS;
            for (int u = sc.F; u < nu; u++) {
                while (arr < u - sc.F + 1) { mbar_wait(full + as * 8, ap); arr++; if (++as == NS) { as = 0; ap ^= 1; } }
                int need = max(u - NS + 1, (int)sc.need[u]);
                while (rel < need) { mbar_wait(empty + rs * 8, rp); rel++; if (++rs == NS) { rs = 0; rp ^= 1; } }
                size_t off = (size_t)(blockIdx.x + (u >> 3) * gridDim.x) * (UPC * CHB) + (u & 7) * CHB;
                mbar_expect_tx(full + s * 8, CHB);
                bulk_load(ring + s * CHB, x + off, CHB, full + s * 8, pol);
                if (++s == NS) s = 0;
                int p0 = sc.pf[u], p1 = sc.pf[u + 1];
                for (int p = p0; p < p1; p++) {
                    int pu = sc.pf_start + (p >> 3);
                    if (pu < nu) {
                        size_t off2 = (size_t)(blockIdx.x + (pu >> 3) * gridDim.x) * (UPC * CHB) + (pu & 7) * CHB + (p & 7) * (CHB / 8);
                        bulk_prefetch(x + off2, CHB / 8);
                    }
                }
            }
        }
        return;
    }
    if (tid < nch) { int c = blockIdx.x + tid * gridDim.x; gb[tid * 2] = __bfloat162float(g[c]); gb[tid * 2 + 1] = __bfloat162float(b[c]); }
    const int warp = tid >> 5, lane = tid & 31;
    uint4 d[UPC][2];
    float K, s0 = 0, s1 = 0, q0 = 0, q1 = 0, A, B;
    int cs = 0, cp = 0;
    auto fetch = [&](int j) {
        mbar_wait(full + cs * 8, cp);
        uint32_t a = ring + cs * CHB;
        if (j == 0) { uint32_t k; asm volatile("ld.shared.u32 %0, [%1];" : "=r"(k) : "r"(a) : "memory"); K = bf_lo(k); }
        d[j][0] = lds128(a + tid * 16);
        d[j][1] = lds128(a + CHB / 2 + tid * 16);
        acc4(d[j][0], K, s0, s1, q0, q1);
        __syncwarp();
        if (lane == 0) mbar_arrive(empty + cs * 8);
        acc4(d[j][1], K, s0, s1, q0, q1);
        if (++cs == NS) { cs = 0; cp ^= 1; }
    };
    auto reduce = [&](int k) {
        float s = s0 + s1, q = q0 + q1;
#pragma unroll
        for (int o = 16; o; o >>= 1) { s += __shfl_xor_sync(~0u, s, o); q += __shfl_xor_sync(~0u, q, o); }
        float* r = red + (k & 1) * 32;
        if (lane == 0) { r[warp * 2] = s; r[warp * 2 + 1] = q; }
        asm volatile("bar.sync 1, %0;" :: "n"(NCONS) : "memory");
        float v = r[lane];
        float gg = gb[k * 2], bb = gb[k * 2 + 1];
#pragma unroll
        for (int o = 2; o < 32; o <<= 1) v += __shfl_xor_sync(~0u, v, o);
        s = __shfl_sync(~0u, v, 0); q = __shfl_sync(~0u, v, 1);
        const float inv = 1.0f / 65536.0f;
        float m = s * inv;
        float var = fmaxf(q * inv - m * m, 0.f);
        float rstd = rsqrtf(var + 1e-5f);
        A = gg * rstd;
        B = bb - (K + m) * A;
        s0 = s1 = q0 = q1 = 0;
    };
#pragma unroll
    for (int j = 0; j < UPC; j++) fetch(j);
    reduce(0);
    for (int k = 0; k < nch; k++) {
        bool hasNext = k + 1 < nch;
        char* yo = y + (size_t)(blockIdx.x + k * gridDim.x) * (UPC * CHB) + tid * 16;
        float cA = A, cB = B;
#pragma unroll
        for (int j = 0; j < UPC; j++) {
            int w = k * UPC + j;
            int pa = sc.pace[w];
            if (pa >= 0 && pa < nu) mbar_wait(full + (pa % NS) * 8, (pa / NS) & 1);
            { uint32_t tw = sc.tw[w]; if (tw) { while (gtime32() - tstart < tw) { __nanosleep(20); } } }
            st_pol(yo + j * CHB, norm4(d[j][0], cA, cB), pol);
            st_pol(yo + j * CHB + CHB / 2, norm4(d[j][1], cA, cB), pol);
            if (hasNext) fetch(j);
        }
        if (hasNext) reduce(k + 1);
    }
}

Sched make_sched() {
    const float a0 = 13, aslope = 1.5f, thr = 2.0f, T1 = 26.0f, tau = 0.73f, tau2 = 0.62f;
    const int nw_paced = 12, pf_start = 34, pf_u0 = 14, pf_u1 = 34, F = 4, w1 = 12, w2 = 24;
    Sched s; memset(&s, 0, sizeof s);
    for (int u = 0; u < MAXU; u++) {
        int need = 0;
        if (u >= pf_start) need = (pf_start - NS + 1) + (int)((u - pf_start) * thr);
        if (need > u - 2) need = u - 2;
        s.need[u] = (signed char)need;
    }
    for (int w = 0; w < MAXU; w++) {
        int a = w < nw_paced ? (int)(a0 + aslope * w) : -1;
        if (a >= MAXU) a = MAXU - 1;
        while (a >= 0 && ((a - NS + 1 > s.need[a] ? a - NS + 1 : s.need[a]) > 8 + w)) a--;
        s.pace[w] = (signed char)a;
        s.tw[w] = w >= w2 ? (int)(1000 * (T1 + (w2 - w1) * tau + (w - w2) * tau2)) : w >= w1 ? (int)(1000 * (T1 + (w - w1) * tau)) : 0;
    }
    int tot = (MAXU - pf_start) * 8;
    for (int r = 0; r <= MAXU; r++)
        s.pf[r] = (unsigned char)(r <= pf_u0 ? 0 : r >= pf_u1 ? tot : tot * (r - pf_u0) / (pf_u1 - pf_u0));
    s.pf_start = pf_start; s.F = F;
    return s;
}

}

extern "C" void kernel_launch(void* const* d_in, const int* in_sizes, int n_in, void* d_out, int out_size) {
    const char* x = (const char*)d_in[0];
    const __nv_bfloat16* g = (const __nv_bfloat16*)d_in[1];
    const __nv_bfloat16* b = (const __nv_bfloat16*)d_in[2];
    int nchan = in_sizes[1];
    cudaFuncSetAttribute(instnorm_kernel, cudaFuncAttributeMaxDynamicSharedMemorySize, SMEM);
    instnorm_kernel<<<GRID, NCONS + 32, SMEM>>>(x, g, b, (char*)d_out, nchan, make_sched());
}
```

```cpp
#include <cuda_runtime.h>
#include <cuda_bf16.h>
#include <stdint.h>
#include <string.h>

namespace inorm {

constexpr int HW = 65536;
constexpr int CHB = 16384;
constexpr int UPC = HW * 2 / CHB;
constexpr int NCH = 5;
constexpr int NU = NCH * UPC;
constexpr int GRID = 128;
constexpr int NS = 14;
constexpr int RD = 13;
constexpr int NWR = 256;
constexpr int V = CHB / 16 / NWR;
constexpr int NSW = 3;
constexpr int THREADS = 128 + NWR;
constexpr int SMEM = NS * CHB + 1536;
constexpr int SPIN_LIMIT = 1 << 20;

struct Sched {
    uint32_t ld[NU + 1];
    uint32_t wr[NU];
    int F;
    int pf_unit;
    int w1, w2, w3;
    uint32_t T1, tau1, tau2, tau3;
    uint32_t delta;
    uint32_t thd;
    int wf;
};

__device__ __forceinline__ uint32_t smem_u32(const void* p) { return (uint32_t)__cvta_generic_to_shared(p); }
__device__ __forceinline__ void mbar_init(uint32_t bar, uint32_t cnt) { asm volatile("mbarrier.init.shared::cta.b64 [%0], %1;" :: "r"(bar), "r"(cnt) : "memory"); }
__device__ __forceinline__ void mbar_expect_tx(uint32_t bar, uint32_t bytes) { asm volatile("mbarrier.arrive.expect_tx.shared::cta.b64 _, [%0], %1;" :: "r"(bar), "r"(bytes) : "memory"); }
__device__ __forceinline__ void mbar_arrive(uint32_t bar) { asm volatile("mbarrier.arrive.shared::cta.b64 _, [%0];" :: "r"(bar) : "memory"); }
__device__ __forceinline__ bool mbar_try(uint32_t bar, uint32_t parity) {
    uint32_t ok;
    asm volatile("{\n.reg .pred p;\nmbarrier.try_wait.parity.shared::cta.b64 p, [%1], %2;\nselp.u32 %0, 1, 0, p;\n}" : "=r"(ok) : "r"(bar), "r"(parity) : "memory");
    return ok;
}
__device__ __forceinline__ bool mbar_test(uint32_t bar, uint32_t parity) {
    uint32_t ok;
    asm volatile("{\n.reg .pred p;\nmbarrier.test_wait.parity.shared::cta.b64 p, [%1], %2;\nselp.u32 %0, 1, 0, p;\n}" : "=r"(ok) : "r"(bar), "r"(parity) : "memory");
    return ok;
}
__device__ __forceinline__ void mbar_wait(uint32_t bar, uint32_t parity) {
    int it = 0;
#pragma unroll 1
    while (!mbar_try(bar, parity)) { if (++it > SPIN_LIMIT) break; }
}
__device__ __forceinline__ void bulk_load(uint32_t dst, const void* src, uint32_t bar, uint64_t pol) {
    mbar_expect_tx(bar, CHB);
    asm volatile("cp.async.bulk.shared::cluster.global.mbarrier::complete_tx::bytes.L2::cache_hint [%0], [%1], %2, [%3], %4;"
                 :: "r"(dst), "l"(src), "n"(CHB), "r"(bar), "l"(pol) : "memory");
}
__device__ __forceinline__ void bulk_prefetch(const void* src, uint32_t bytes) {
    asm volatile("cp.async.bulk.prefetch.L2.global [%0], %1;" :: "l"(src), "r"(bytes) : "memory");
}
__device__ __forceinline__ uint64_t policy_evict_first() { uint64_t p; asm volatile("createpolicy.fractional.L2::evict_first.b64 %0, 1.0;" : "=l"(p)); return p; }
__device__ __forceinline__ uint4 lds128(uint32_t a) {
    uint4 v; asm volatile("ld.shared.v4.u32 {%0,%1,%2,%3}, [%4];" : "=r"(v.x), "=r"(v.y), "=r"(v.z), "=r"(v.w) : "r"(a) : "memory"); return v;
}
__device__ __forceinline__ uint32_t lds_vol(uint32_t a) { uint32_t v; asm volatile("ld.volatile.shared.u32 %0, [%1];" : "=r"(v) : "r"(a) : "memory"); return v; }
__device__ __forceinline__ void sts_vol(uint32_t a, uint32_t v) { asm volatile("st.volatile.shared.u32 [%0], %1;" :: "r"(a), "r"(v) : "memory"); }
__device__ __forceinline__ void stg128(void* p, uint4 v, uint64_t pol) {
    asm volatile("st.global.L2::cache_hint.v4.u32 [%0], {%1,%2,%3,%4}, %5;" :: "l"(p), "r"(v.x), "r"(v.y), "r"(v.z), "r"(v.w), "l"(pol) : "memory");
}
__device__ __forceinline__ uint32_t now_ns() { uint32_t t; asm volatile("mov.u32 %0, %globaltimer_lo;" : "=r"(t)); return t; }
__device__ __forceinline__ bool elect_one() { uint32_t p; asm volatile("{\n.reg .pred p;\nelect.sync _|p, 0xffffffff;\nselp.u32 %0, 1, 0, p;\n}" : "=r"(p)); return p; }
__device__ __forceinline__ float bf_lo(uint32_t u) { return __uint_as_float(u << 16); }
__device__ __forceinline__ float bf_hi(uint32_t u) { return __uint_as_float(u & 0xffff0000u); }
__device__ __forceinline__ uint32_t pack_bf(float lo, float hi) { uint32_t r; asm("cvt.rn.bf16x2.f32 %0, %1, %2;" : "=r"(r) : "f"(hi), "f"(lo)); return r; }
__device__ __forceinline__ uint32_t sub_bf2(uint32_t a, uint32_t b) { uint32_t r; asm("sub.rn.bf16x2 %0, %1, %2;" : "=r"(r) : "r"(a), "r"(b)); return r; }
__device__ __forceinline__ void mma_k8(float (&d)[4], uint32_t a0, uint32_t a1, uint32_t b0) {
    asm("mma.sync.aligned.m16n8k8.row.col.f32.bf16.bf16.f32 {%0,%1,%2,%3}, {%4,%5}, {%6}, {%0,%1,%2,%3};"
        : "+f"(d[0]), "+f"(d[1]), "+f"(d[2]), "+f"(d[3]) : "r"(a0), "r"(a1), "r"(b0));
}
__device__ __forceinline__ void mma_rowsum(float (&d)[4], uint32_t a0, uint32_t a1, uint32_t a2, uint32_t a3) {
    asm("mma.sync.aligned.m16n8k16.row.col.f32.bf16.bf16.f32 {%0,%1,%2,%3}, {%4,%5,%6,%7}, {%8,%8}, {%0,%1,%2,%3};"
        : "+f"(d[0]), "+f"(d[1]), "+f"(d[2]), "+f"(d[3]) : "r"(a0), "r"(a1), "r"(a2), "r"(a3), "r"(0x3f803f80u));
}
__device__ __forceinline__ void accumulate(uint4 v, uint32_t K2, float (&S)[4], float (&Q0)[4], float (&Q1)[4]) {
    uint32_t d0 = sub_bf2(v.x, K2), d1 = sub_bf2(v.y, K2), d2 = sub_bf2(v.z, K2), d3 = sub_bf2(v.w, K2);
    mma_k8(Q0, d0, d1, d0);
    mma_k8(Q1, d0, d1, d1);
    mma_rowsum(S, d0, d1, d2, d3);
    mma_k8(Q0, d2, d3, d2);
    mma_k8(Q1, d2, d3, d3);
}
__device__ __forceinline__ uint4 normalise(uint4 v, float A, float B) {
    return make_uint4(pack_bf(fmaf(bf_lo(v.x), A, B), fmaf(bf_hi(v.x), A, B)), pack_bf(fmaf(bf_lo(v.y), A, B), fmaf(bf_hi(v.y), A, B)),
                      pack_bf(fmaf(bf_lo(v.z), A, B), fmaf(bf_hi(v.z), A, B)), pack_bf(fmaf(bf_lo(v.w), A, B), fmaf(bf_hi(v.w), A, B)));
}

__global__ void __launch_bounds__(THREADS, 1)
instnorm_kernel(const char* __restrict__ x, const __nv_bfloat16* __restrict__ g, const __nv_bfloat16* __restrict__ b,
                char* __restrict__ y, const __grid_constant__ Sched sc) {
    extern __shared__ __align__(128) char smem[];
    const uint32_t ring = smem_u32(smem);
    const uint32_t full = ring + NS * CHB, empty = full + NS * 8, statb = empty + NS * 8;
    float2* ab = (float2*)(smem + NS * CHB + 272);
    float2* red = ab + NCH;
    const uint32_t shw = ring + NS * CHB + 1016;
    uint32_t* wtab = (uint32_t*)(smem + NS * CHB + 1024);
    uint32_t* ltab = wtab + NU;
    const char* xb = x + (size_t)blockIdx.x * (UPC * CHB);
    const uint64_t pol = policy_evict_first();
    const uint32_t tstart = now_ns();
    if (threadIdx.x == 0) {
        mbar_init(full, 1);
        bulk_load(ring, xb, full, pol);
        mbar_init(full + 8, 1);
        bulk_load(ring + CHB, xb + CHB, full + 8, pol);
#pragma unroll
        for (int s = 2; s < NS; s++) mbar_init(full + s * 8, 1);
        for (int u = 2; u < sc.F; u++) bulk_load(ring + u * CHB, xb + u * CHB, full + u * 8, pol);
#pragma unroll
        for (int s = 0; s < NS; s++) mbar_init(empty + s * 8, NWR / 32 + NSW);
#pragma unroll
        for (int s = 0; s < NCH; s++) mbar_init(statb + s * 8, 1);
        asm volatile("fence.mbarrier_init.release.cluster;" ::: "memory");
    }
    if (threadIdx.x >= 128 && threadIdx.x <= 128 + NU) {
        int i = threadIdx.x - 128;
        ltab[i] = sc.ld[i];
        if (i < NU) wtab[i] = sc.wr[i]; else sts_vol(shw, 0);
    }
    const int wid = __shfl_sync(~0u, threadIdx.x >> 5, 0);
    const int lane = threadIdx.x & 31;
    __syncthreads();

    if (wid < 4) {
        asm volatile("setmaxnreg.dec.sync.aligned.u32 40;");
        if (wid == 0) {
            if (lane == 0) {
                const int F = sc.F;
                const char* pfb = xb + (size_t)(NCH - 1) * (GRID * UPC * CHB) + (sc.pf_unit % UPC) * CHB;
                int rel = 0, rs = 0, rp = 0;
                int as = 0, ap = 0;
                int s = F;
                for (int u = F; u < NU; u++) {
                    const uint32_t e = ltab[u], e1 = ltab[u + 1];
                    mbar_wait(full + as * 8, ap);
                    if (++as == NS) { as = 0; ap ^= 1; }
                    const int need = (e >> 16) & 0xff;
                    while (rel < need) { mbar_wait(empty + rs * 8, rp); rel++; if (++rs == NS) { rs = 0; rp ^= 1; } }
                    while (now_ns() - tstart < (e & 0xffff) + lds_vol(shw)) {}
                    bulk_load(ring + s * CHB, xb + (size_t)(u / UPC) * (GRID * UPC * CHB) + (u % UPC) * CHB, full + s * 8, pol);
                    if (++s == NS) s = 0;
                    const int p0 = e >> 24, p1 = e1 >> 24;
                    if (p1 > p0) bulk_prefetch(pfb + p0 * (CHB / 8), (p1 - p0) * (CHB / 8));
                }
            }
        } else {
            const int sw = wid - 1;
            const uint32_t delta = sc.delta;
            float gv = 0.f, bv = 0.f;
            if (sw == 0 && lane < NCH) { int c = blockIdx.x + lane * GRID; gv = __bfloat162float(g[c]); bv = __bfloat162float(b[c]); }
            const bool diag = (lane & 3) == (lane >> 3), odd = (lane >> 2) & 1;
            uint32_t s = 0, p = 0;
#pragma unroll 1
            for (int c = 0; c < NCH; c++) {
                float S[4] = {0, 0, 0, 0}, Q0[4] = {0, 0, 0, 0}, Q1[4] = {0, 0, 0, 0};
                uint32_t K2 = 0;
#pragma unroll 1
                for (int j = 0; j < UPC; j++) {
                    if (sw == NSW - 1) {
                        const uint32_t dl = wtab[c * UPC + j] >> 16;
#pragma unroll 1
                        while (!mbar_test(full + s * 8, p)) { if (now_ns() - tstart > dl) { sts_vol(shw, delta); break; } __nanosleep(32); }
                    }
                    mbar_wait(full + s * 8, p);
                    uint32_t a = ring + s * CHB + lane * 16;
                    if (j == 0) {
                        uint4 k = lds128(a);
                        float z[4] = {0, 0, 0, 0};
                        mma_rowsum(z, k.x, k.y, k.z, k.w);
                        float kk = (z[0] + z[2]) * (1.0f / 32.0f);
                        K2 = pack_bf(kk, kk);
                    }
                    a += sw * 512;
                    uint4 v0 = lds128(a), v1 = lds128(a + 1536);
#pragma unroll
                    for (int r = 0; r < 10; r += 2) {
                        accumulate(v0, K2, S, Q0, Q1);
                        if (r + 2 < 10 || sw < 2) v0 = lds128(a + (r + 2) * 1536);
                        accumulate(v1, K2, S, Q0, Q1);
                        if (r + 3 < 10) v1 = lds128(a + (r + 3) * 1536);
                    }
                    __syncwarp();
                    if (elect_one()) mbar_arrive(empty + s * 8);
                    if (sw < 2) accumulate(v0, K2, S, Q0, Q1);
                    if (++s == NS) { s = 0; p ^= 1; }
                }
                float2* rr = red + (c & 1) * (NSW * 8);
                if (diag) rr[sw * 8 + (lane >> 2)] = make_float2(S[0] + S[2], odd ? Q0[1] + Q1[3] : Q0[0] + Q1[2]);
                asm volatile("bar.sync 1, 96;" ::: "memory");
                if (sw == 0) {
                    constexpr float NG = HW / 8;
                    const int gq = lane >> 2;
                    const float2 a0 = rr[gq], a1 = rr[8 + gq], a2 = rr[16 + gq];
                    const float sg = a0.x + a1.x + a2.x, qg = a0.y + a1.y + a2.y;
                    const float mg = bf_lo(K2) + sg * (1.0f / NG);
                    float m = mg;
#pragma unroll
                    for (int o = 4; o < 32; o <<= 1) m += __shfl_xor_sync(~0u, m, o);
                    m *= 0.125f;
                    float q = (qg - sg * sg * (1.0f / NG)) + NG * (mg - m) * (mg - m);
#pragma unroll
                    for (int o = 4; o < 32; o <<= 1) q += __shfl_xor_sync(~0u, q, o);
                    float var = q * (1.0f / HW);
                    var = var < 0.f ? 0.f : var;
                    const float rstd = rsqrtf(var + 1e-5f);
                    if (lane == c) { float A = gv * rstd; ab[c] = make_float2(A, bv - m * A); mbar_arrive(statb + c * 8); }
                }
            }
        }
    } else {
        asm volatile("setmaxnreg.inc.sync.aligned.u32 232;");
        const int tid = threadIdx.x - 128;
        const int w1 = sc.w1, w2 = sc.w2, w3 = sc.w3, wf = sc.wf;
        const uint32_t tau1 = sc.tau1, tau2 = sc.tau2, tau3 = sc.tau3, delta = sc.delta, thd = sc.thd, fstep = 256 / (NU - sc.wf);
        uint32_t tnext = tstart + sc.T1, tlast = 0;
        uint4 R[RD][V];
        float A, B;
        uint32_t cs = 0;
        int fu = 0;
        int known = 0; uint32_t ks = 0, kp = 0;
        int w = 0;
        const uint32_t ta = ring + tid * 16;
        char* yo = y + (size_t)blockIdx.x * (UPC * CHB) + tid * 16;
        auto learn = [&](int n) { while (known < n) { mbar_wait(full + ks * 8, kp); known++; if (++ks == NS) { ks = 0; kp ^= 1; } } };
        auto fetch = [&](uint4 (&dst)[V]) {
            learn(++fu);
            const uint32_t a = ta + cs * CHB;
#pragma unroll
            for (int i = 0; i < V; i++) dst[i] = lds128(a + i * (NWR * 16));
            __syncwarp();
            if (elect_one()) mbar_arrive(empty + cs * 8);
            if (++cs == NS) cs = 0;
        };
        auto step = [&](uint4 (&cur)[V], uint4 (&nxt)[V]) {
            if (w < w1) learn(__shfl_sync(~0u, wtab[w] & 0xff, 0));
            else {
                uint32_t sh = __shfl_sync(~0u, lds_vol(shw), 0);
                uint32_t now = now_ns();
                if (sh == 0 && w > w1 && w <= wf && now - tlast > thd) { sh = delta; sts_vol(shw, delta); }
                const uint32_t fade = w < wf ? 256u : (uint32_t)(NU - 1 - w) * fstep;
                while ((int)(now - tnext - (sh * fade >> 8)) < 0) { __nanosleep(20); sh = __shfl_sync(~0u, lds_vol(shw), 0); now = now_ns(); }
                tlast = now;
                tnext += w >= w3 ? tau3 : w >= w2 ? tau2 : tau1;
            }
#pragma unroll
            for (int i = 0; i < V; i++) stg128(yo + i * (NWR * 16), cur[i], pol);
            yo += CHB;
            w++;
            if (w < NU) {
                if (w % UPC == 0) {
                    mbar_wait(statb + (w / UPC) * 8, 0);
                    const float2 v = ab[w / UPC]; A = v.x; B = v.y;
                    yo += (size_t)(GRID - 1) * UPC * CHB;
                }
#pragma unroll
                for (int i = 0; i < V; i++) nxt[i] = normalise(nxt[i], A, B);
            }
        };
#pragma unroll
        for (int j = 0; j < UPC; j++) fetch(R[j]);
        mbar_wait(statb, 0);
        { const float2 v = ab[0]; A = v.x; B = v.y; }
#pragma unroll
        for (int i = 0; i < V; i++) R[0][i] = normalise(R[0][i], A, B);
#define INORM_STEP(J) { \
            step(R[J], R[((J) + 1) % RD]); \
            if ((J) == (NU - 1) % RD && w == NU) break; \
            if ((J) < RD - UPC && w <= RD - UPC) { fetch(R[(UPC + 2 * (J)) % RD]); fetch(R[(UPC + 2 * (J) + 1) % RD]); } \
            else if (w + RD <= NU) fetch(R[J]); }
        static_assert(RD == 13, "unrolled below");
#pragma unroll 1
        while (true) {
            INORM_STEP(0) INORM_STEP(1) INORM_STEP(2) INORM_STEP(3) INORM_STEP(4) INORM_STEP(5) INORM_STEP(6)
            INORM_STEP(7) INORM_STEP(8) INORM_STEP(9) INORM_STEP(10) INORM_STEP(11) INORM_STEP(12)
        }
#undef INORM_STEP
    }
}

__global__ void __launch_bounds__(1024) instnorm_generic(const __nv_bfloat16* __restrict__ x, const __nv_bfloat16* __restrict__ g,
                                                         const __nv_bfloat16* __restrict__ b, __nv_bfloat16* __restrict__ y, int hw) {
    __shared__ float red[32];
    const __nv_bfloat16* xc = x + (size_t)blockIdx.x * hw;
    auto block_sum = [&](float v) {
        for (int o = 16; o; o >>= 1) v += __shfl_xor_sync(~0u, v, o);
        __syncthreads();
        if ((threadIdx.x & 31) == 0) red[threadIdx.x >> 5] = v;
        __syncthreads();
        v = red[threadIdx.x & 31];
        for (int o = 16; o; o >>= 1) v += __shfl_xor_sync(~0u, v, o);
        return v;
    };
    float s = 0.f;
    for (int i = threadIdx.x; i < hw; i += 1024) s += __bfloat162float(xc[i]);
    const float m = block_sum(s) / hw;
    float q = 0.f;
    for (int i = threadIdx.x; i < hw; i += 1024) { float d = __bfloat162float(xc[i]) - m; q += d * d; }
    const float A = __bfloat162float(g[blockIdx.x]) * rsqrtf(block_sum(q) / hw + 1e-5f), B = __bfloat162float(b[blockIdx.x]);
    for (int i = threadIdx.x; i < hw; i += 1024) y[(size_t)blockIdx.x * hw + i] = __float2bfloat16((__bfloat162float(xc[i]) - m) * A + B);
}

struct Params {
    int F = 5;
    float a0 = 9.29f, aslope = 2.4f;
    int w1 = 12, pf_unit = 38;
    float pf_u0 = 13.4f, pf_u1 = 38.f;
    float n0 = 17.f, thr = 2.f;
    float T1 = 25.85f, tau1 = 0.641f; int w2 = 28; float tau2 = 0.628f; int w3 = 38; float tau3 = 0.6f;
    float Tl = -0.41f, taul = 0.637f;
    float delta = 1.5f, thd = 0.6f; int wf = 34;
    float dl = 2.95f, dl_early = 0.4f, dl_mid = 0.15f, dl_late = 0.6f;
};

inline Sched make_sched(const Params& p) {
    auto imin = [](int a, int b) { return a < b ? a : b; };
    auto imax = [](int a, int b) { return a > b ? a : b; };
    auto fetched_before = [&](int w) { return imin(NU, imin(RD + w, UPC + 2 * w)); };
    Sched s; memset(&s, 0, sizeof s);
    int need[NU];
    const int tot = (NU - p.pf_unit) * 8;
    for (int u = 0; u <= NU; u++) {
        const int pf = u <= p.pf_u0 ? 0 : u >= p.pf_u1 ? tot : (int)(tot * (u - p.pf_u0) / (p.pf_u1 - p.pf_u0));
        s.ld[u] = (uint32_t)pf << 24;
        if (u == NU) break;
        need[u] = imax(0, u - NS + 1);
        if (u >= p.pf_unit) need[u] = imax(need[u], imin(u - 1, fetched_before(imin(NU - 1, (int)(p.n0 + (u - p.pf_unit) * p.thr)))));
        const float t = p.Tl + (u + pf / 8.0f) * p.taul;
        s.ld[u] |= (uint32_t)need[u] << 16 | (u < p.pf_unit ? (uint32_t)imax(0, (int)(1000 * t)) : 0u);
        const float dl = t + p.dl + (u > 30 ? p.dl_late : u > 20 ? p.dl_mid : u >= 2 && u < p.F ? p.dl_early : 0.f);
        s.wr[u] = (u < p.pf_unit - 1 ? (uint32_t)(1000 * dl) : 0xffffu) << 16;
    }
    for (int w = 0; w < p.w1; w++) {
        int a = imin(NU - 1, (int)(p.a0 + p.aslope * w));
        while (a >= 0 && need[a] > fetched_before(w)) a--;
        s.wr[w] |= (uint32_t)(a + 1);
    }
    s.F = p.F; s.pf_unit = p.pf_unit; s.w1 = p.w1; s.w2 = p.w2; s.w3 = p.w3; s.wf = p.wf;
    s.T1 = (uint32_t)(1000 * p.T1 + .5f); s.tau1 = (uint32_t)(1000 * p.tau1 + .5f); s.tau2 = (uint32_t)(1000 * p.tau2 + .5f);
    s.tau3 = (uint32_t)(1000 * p.tau3 + .5f); s.delta = (uint32_t)(1000 * p.delta + .5f); s.thd = (uint32_t)(1000 * p.thd + .5f);
    return s;
}

}

extern "C" void kernel_launch(void* const* d_in, const int* in_sizes, int n_in, void* d_out, int out_size) {
    using namespace inorm;
    const __nv_bfloat16* x = (const __nv_bfloat16*)d_in[0];
    const __nv_bfloat16* g = (const __nv_bfloat16*)d_in[1];
    const __nv_bfloat16* b = (const __nv_bfloat16*)d_in[2];
    const int C = in_sizes[1];
    if (C == GRID * NCH && in_sizes[0] == C * HW) {
        cudaFuncSetAttribute(instnorm_kernel, cudaFuncAttributeMaxDynamicSharedMemorySize, SMEM);
        instnorm_kernel<<<GRID, THREADS, SMEM>>>((const char*)x, g, b, (char*)d_out, make_sched(Params()));
    } else {
        instnorm_generic<<<C, 1024>>>(x, g, b, (__nv_bfloat16*)d_out, in_sizes[0] / C);
    }
}
```

```cpp
#include <cuda_runtime.h>
#include <cuda_bf16.h>
#include <stdint.h>
#include <string.h>

namespace inorm {

constexpr int HW = 65536;
constexpr int CHB = 16384;
constexpr int UPC = HW * 2 / CHB;
constexpr int NCH = 5;
constexpr int NU = NCH * UPC;
constexpr int GRID = 128;
constexpr int NS = 14;
constexpr int RD = 13;
constexpr int NWR = 256;
constexpr int V = CHB / 16 / NWR;
constexpr int NSW = 3;
constexpr int THREADS = 128 + NWR;
constexpr int SMEM = NS * CHB + 1536;
constexpr int SPIN_LIMIT = 1 << 20;

struct Sched {
    uint32_t ld[NU + 1];
    uint32_t wr[NU];
    int F;
    int pf_unit;
    int w1, w2, w3;
    uint32_t T1, tau1, tau2, tau3;
    uint32_t delta;
    uint32_t thd;
    int wf;
};

__device__ __forceinline__ uint32_t smem_u32(const void* p) { return (uint32_t)__cvta_generic_to_shared(p); }
__device__ __forceinline__ void mbar_init(uint32_t bar, uint32_t cnt) { asm volatile("mbarrier.init.shared::cta.b64 [%0], %1;" :: "r"(bar), "r"(cnt) : "memory"); }
__device__ __forceinline__ void mbar_expect_tx(uint32_t bar, uint32_t bytes) { asm volatile("mbarrier.arrive.expect_tx.shared::cta.b64 _, [%0], %1;" :: "r"(bar), "r"(bytes) : "memory"); }
__device__ __forceinline__ void mbar_arrive(uint32_t bar) { asm volatile("mbarrier.arrive.shared::cta.b64 _, [%0];" :: "r"(bar) : "memory"); }
__device__ __forceinline__ bool mbar_try(uint32_t bar, uint32_t parity) {
    uint32_t ok;
    asm volatile("{\n.reg .pred p;\nmbarrier.try_wait.parity.shared::cta.b64 p, [%1], %2;\nselp.u32 %0, 1, 0, p;\n}" : "=r"(ok) : "r"(bar), "r"(parity) : "memory");
    return ok;
}
__device__ __forceinline__ bool mbar_test(uint32_t bar, uint32_t parity) {
    uint32_t ok;
    asm volatile("{\n.reg .pred p;\nmbarrier.test_wait.parity.shared::cta.b64 p, [%1], %2;\nselp.u32 %0, 1, 0, p;\n}" : "=r"(ok) : "r"(bar), "r"(parity) : "memory");
    return ok;
}
__device__ __forceinline__ void mbar_wait(uint32_t bar, uint32_t parity) {
    int it = 0;
#pragma unroll 1
    while (!mbar_try(bar, parity)) { if (++it > SPIN_LIMIT) break; }
}
__device__ __forceinline__ void bulk_load(uint32_t dst, const void* src, uint32_t bar, uint64_t pol) {
    mbar_expect_tx(bar, CHB);
    asm volatile("cp.async.bulk.shared::cluster.global.mbarrier::complete_tx::bytes.L2::cache_hint [%0], [%1], %2, [%3], %4;"
                 :: "r"(dst), "l"(src), "n"(CHB), "r"(bar), "l"(pol) : "memory");
}
__device__ __forceinline__ void bulk_prefetch(const void* src, uint32_t bytes) {
    asm volatile("cp.async.bulk.prefetch.L2.global [%0], %1;" :: "l"(src), "r"(bytes) : "memory");
}
__device__ __forceinline__ uint64_t policy_evict_first() { uint64_t p; asm volatile("createpolicy.fractional.L2::evict_first.b64 %0, 1.0;" : "=l"(p)); return p; }
__device__ __forceinline__ uint4 lds128(uint32_t a) {
    uint4 v; asm volatile("ld.shared.v4.u32 {%0,%1,%2,%3}, [%4];" : "=r"(v.x), "=r"(v.y), "=r"(v.z), "=r"(v.w) : "r"(a) : "memory"); return v;
}
__device__ __forceinline__ uint32_t lds_vol(uint32_t a) { uint32_t v; asm volatile("ld.volatile.shared.u32 %0, [%1];" : "=r"(v) : "r"(a) : "memory"); return v; }
__device__ __forceinline__ void sts_vol(uint32_t a, uint32_t v) { asm volatile("st.volatile.shared.u32 [%0], %1;" :: "r"(a), "r"(v) : "memory"); }
__device__ __forceinline__ void stg128(void* p, uint4 v, uint64_t pol) {
    asm volatile("st.global.L2::cache_hint.v4.u32 [%0], {%1,%2,%3,%4}, %5;" :: "l"(p), "r"(v.x), "r"(v.y), "r"(v.z), "r"(v.w), "l"(pol) : "memory");
}
__device__ __forceinline__ uint32_t now_ns() { uint32_t t; asm volatile("mov.u32 %0, %globaltimer_lo;" : "=r"(t)); return t; }
__device__ __forceinline__ bool elect_one() { uint32_t p; asm volatile("{\n.reg .pred p;\nelect.sync _|p, 0xffffffff;\nselp.u32 %0, 1, 0, p;\n}" : "=r"(p)); return p; }
__device__ __forceinline__ float bf_lo(uint32_t u) { return __uint_as_float(u << 16); }
__device__ __forceinline__ float bf_hi(uint32_t u) { return __uint_as_float(u & 0xffff0000u); }
__device__ __forceinline__ uint32_t pack_bf(float lo, float hi) { uint32_t r; asm("cvt.rn.bf16x2.f32 %0, %1, %2;" : "=r"(r) : "f"(hi), "f"(lo)); return r; }
__device__ __forceinline__ uint32_t sub_bf2(uint32_t a, uint32_t b) { uint32_t r; asm("sub.rn.bf16x2 %0, %1, %2;" : "=r"(r) : "r"(a), "r"(b)); return r; }
__device__ __forceinline__ void mma_k8(float (&d)[4], uint32_t a0, uint32_t a1, uint32_t b0) {
    asm("mma.sync.aligned.m16n8k8.row.col.f32.bf16.bf16.f32 {%0,%1,%2,%3}, {%4,%5}, {%6}, {%0,%1,%2,%3};"
        : "+f"(d[0]), "+f"(d[1]), "+f"(d[2]), "+f"(d[3]) : "r"(a0), "r"(a1), "r"(b0));
}
__device__ __forceinline__ void mma_rowsum(float (&d)[4], uint32_t a0, uint32_t a1, uint32_t a2, uint32_t a3) {
    asm("mma.sync.aligned.m16n8k16.row.col.f32.bf16.bf16.f32 {%0,%1,%2,%3}, {%4,%5,%6,%7}, {%8,%8}, {%0,%1,%2,%3};"
        : "+f"(d[0]), "+f"(d[1]), "+f"(d[2]), "+f"(d[3]) : "r"(a0), "r"(a1), "r"(a2), "r"(a3), "r"(0x3f803f80u));
}
__device__ __forceinline__ void accumulate(uint4 v, uint32_t K2, float (&S)[4], float (&Q0)[4], float (&Q1)[4]) {
    uint32_t d0 = sub_bf2(v.x, K2), d1 = sub_bf2(v.y, K2), d2 = sub_bf2(v.z, K2), d3 = sub_bf2(v.w, K2);
    mma_k8(Q0, d0, d1, d0);
    mma_k8(Q1, d0, d1, d1);
    mma_rowsum(S, d0, d1, d2, d3);
    mma_k8(Q0, d2, d3, d2);
    mma_k8(Q1, d2, d3, d3);
}
__device__ __forceinline__ uint4 normalise(uint4 v, float A, float B) {
    return make_uint4(pack_bf(fmaf(bf_lo(v.x), A, B), fmaf(bf_hi(v.x), A, B)), pack_bf(fmaf(bf_lo(v.y), A, B), fmaf(bf_hi(v.y), A, B)),
                      pack_bf(fmaf(bf_lo(v.z), A, B), fmaf(bf_hi(v.z), A, B)), pack_bf(fmaf(bf_lo(v.w), A, B), fmaf(bf_hi(v.w), A, B)));
}

__global__ void __launch_bounds__(THREADS, 1)
instnorm_kernel(const char* __restrict__ x, const __nv_bfloat16* __restrict__ g, const __nv_bfloat16* __restrict__ b,
                char* __restrict__ y, const __grid_constant__ Sched sc) {
    extern __shared__ __align__(128) char smem[];
    const uint32_t ring = smem_u32(smem);
    const uint32_t full = ring + NS * CHB, empty = full + NS * 8, statb = empty + NS * 8;
    float2* ab = (float2*)(smem + NS * CHB + 272);
    float2* red = ab + NCH;
    const uint32_t shw = ring + NS * CHB + 1016;
    uint32_t* wtab = (uint32_t*)(smem + NS * CHB + 1024);
    uint32_t* ltab = wtab + NU;
    const char* xb = x + (size_t)blockIdx.x * (UPC * CHB);
    const uint64_t pol = policy_evict_first();
    if (threadIdx.x == 0) {
        mbar_init(full, 1);
        bulk_load(ring, xb, full, pol);
        sts_vol(shw + 4, now_ns());
        mbar_init(full + 8, 1);
        bulk_load(ring + CHB, xb + CHB, full + 8, pol);
#pragma unroll
        for (int s = 2; s < NS; s++) mbar_init(full + s * 8, 1);
        for (int u = 2; u < sc.F; u++) bulk_load(ring + u * CHB, xb + u * CHB, full + u * 8, pol);
#pragma unroll
        for (int s = 0; s < NS; s++) mbar_init(empty + s * 8, NWR / 32 + NSW);
#pragma unroll
        for (int s = 0; s < NCH; s++) mbar_init(statb + s * 8, 1);
        asm volatile("fence.mbarrier_init.release.cluster;" ::: "memory");
    }
    if (threadIdx.x >= 128 && threadIdx.x <= 128 + NU) {
        int i = threadIdx.x - 128;
        ltab[i] = sc.ld[i];
        if (i < NU) wtab[i] = sc.wr[i]; else sts_vol(shw, 0);
    }
    const int wid = __shfl_sync(~0u, threadIdx.x >> 5, 0);
    const int lane = threadIdx.x & 31;
    __syncthreads();
    const uint32_t tstart = __shfl_sync(~0u, lds_vol(shw + 4), 0);

    if (wid < 4) {
        asm volatile("setmaxnreg.dec.sync.aligned.u32 40;");
        if (wid == 0) {
            if (lane == 0) {
                const int F = sc.F;
                const char* pfb = xb + (size_t)(NCH - 1) * (GRID * UPC * CHB) + (sc.pf_unit % UPC) * CHB;
                int rel = 0, rs = 0, rp = 0;
                int as = 0, ap = 0;
                int s = F;
                for (int u = F; u < NU; u++) {
                    const uint32_t e = ltab[u], e1 = ltab[u + 1];
                    mbar_wait(full + as * 8, ap);
                    if (++as == NS) { as = 0; ap ^= 1; }
                    const int need = (e >> 16) & 0xff;
                    while (rel < need) { mbar_wait(empty + rs * 8, rp); rel++; if (++rs == NS) { rs = 0; rp ^= 1; } }
                    while (now_ns() - tstart < (e & 0xffff) + lds_vol(shw)) {}
                    bulk_load(ring + s * CHB, xb + (size_t)(u / UPC) * (GRID * UPC * CHB) + (u % UPC) * CHB, full + s * 8, pol);
                    if (++s == NS) s = 0;
                    const int p0 = e >> 24, p1 = e1 >> 24;
                    if (p1 > p0) bulk_prefetch(pfb + p0 * (CHB / 8), (p1 - p0) * (CHB / 8));
                }
            }
        } else {
            const int sw = wid - 1;
            const uint32_t delta = sc.delta;
            float gv = 0.f, bv = 0.f;
            if (sw == 0 && lane < NCH) { int c = blockIdx.x + lane * GRID; gv = __bfloat162float(g[c]); bv = __bfloat162float(b[c]); }
            const bool diag = (lane & 3) == (lane >> 3), odd = (lane >> 2) & 1;
            uint32_t s = 0, p = 0;
#pragma unroll 1
            for (int c = 0; c < NCH; c++) {
                float S[4] = {0, 0, 0, 0}, Q0[4] = {0, 0, 0, 0}, Q1[4] = {0, 0, 0, 0};
                uint32_t K2 = 0;
#pragma unroll 1
                for (int j = 0; j < UPC; j++) {
                    if (sw == NSW - 1) {
                        const uint32_t dl = wtab[c * UPC + j] >> 16;
#pragma unroll 1
                        while (!mbar_test(full + s * 8, p)) { if (now_ns() - tstart > dl) { sts_vol(shw, delta); break; } __nanosleep(32); }
                    }
                    mbar_wait(full + s * 8, p);
                    uint32_t a = ring + s * CHB + lane * 16;
                    if (j == 0) {
                        uint4 k = lds128(a);
                        float z[4] = {0, 0, 0, 0};
                        mma_rowsum(z, k.x, k.y, k.z, k.w);
                        float kk = (z[0] + z[2]) * (1.0f / 32.0f);
                        K2 = pack_bf(kk, kk);
                    }
                    a += sw * 512;
                    uint4 v0 = lds128(a), v1 = lds128(a + 1536);
#pragma unroll
                    for (int r = 0; r < 10; r += 2) {
                        accumulate(v0, K2, S, Q0, Q1);
                        if (r + 2 < 10 || sw < 2) v0 = lds128(a + (r + 2) * 1536);
                        accumulate(v1, K2, S, Q0, Q1);
                        if (r + 3 < 10) v1 = lds128(a + (r + 3) * 1536);
                    }
                    __syncwarp();
                    if (elect_one()) mbar_arrive(empty + s * 8);
                    if (sw < 2) accumulate(v0, K2, S, Q0, Q1);
                    if (++s == NS) { s = 0; p ^= 1; }
                }
                float2* rr = red + (c & 1) * (NSW * 8);
                if (diag) rr[sw * 8 + (lane >> 2)] = make_float2(S[0] + S[2], odd ? Q0[1] + Q1[3] : Q0[0] + Q1[2]);
                asm volatile("bar.sync 1, 96;" ::: "memory");
                if (sw == 0) {
                    constexpr float NG = HW / 8;
                    const int gq = lane >> 2;
                    const float2 a0 = rr[gq], a1 = rr[8 + gq], a2 = rr[16 + gq];
                    const float sg = a0.x + a1.x + a2.x, qg = a0.y + a1.y + a2.y;
                    const float mg = bf_lo(K2) + sg * (1.0f / NG);
                    float m = mg;
#pragma unroll
                    for (int o = 4; o < 32; o <<= 1) m += __shfl_xor_sync(~0u, m, o);
                    m *= 0.125f;
                    float q = (qg - sg * sg * (1.0f / NG)) + NG * (mg - m) * (mg - m);
#pragma unroll
                    for (int o = 4; o < 32; o <<= 1) q += __shfl_xor_sync(~0u, q, o);
                    float var = q * (1.0f / HW);
                    var = var < 0.f ? 0.f : var;
                    const float rstd = rsqrtf(var + 1e-5f);
                    if (lane == c) { float A = gv * rstd; ab[c] = make_float2(A, bv - m * A); mbar_arrive(statb + c * 8); }
                }
            }
        }
    } else {
        asm volatile("setmaxnreg.inc.sync.aligned.u32 232;");
        const int tid = threadIdx.x - 128;
        const int w1 = sc.w1, w2 = sc.w2, w3 = sc.w3, wf = sc.wf;
        const uint32_t tau1 = sc.tau1, tau2 = sc.tau2, tau3 = sc.tau3, delta = sc.delta, thd = sc.thd, fstep = 256 / (NU - sc.wf);
        uint32_t tnext = tstart + sc.T1, tlast = 0;
        uint4 R[RD][V];
        float A, B;
        uint32_t cs = 0;
        int fu = 0;
        int known = 0; uint32_t ks = 0, kp = 0;
        int w = 0;
        const uint32_t ta = ring + tid * 16;
        char* yo = y + (size_t)blockIdx.x * (UPC * CHB) + tid * 16;
        auto learn = [&](int n) { while (known < n) { mbar_wait(full + ks * 8, kp); known++; if (++ks == NS) { ks = 0; kp ^= 1; } } };
        auto fetch = [&](uint4 (&dst)[V]) {
            learn(++fu);
            const uint32_t a = ta + cs * CHB;
#pragma unroll
            for (int i = 0; i < V; i++) dst[i] = lds128(a + i * (NWR * 16));
            __syncwarp();
            if (elect_one()) mbar_arrive(empty + cs * 8);
            if (++cs == NS) cs = 0;
        };
        auto step = [&](uint4 (&cur)[V], uint4 (&nxt)[V]) {
            if (w < w1) learn(__shfl_sync(~0u, wtab[w] & 0xff, 0));
            else {
                uint32_t sh = __shfl_sync(~0u, lds_vol(shw), 0);
                uint32_t now = now_ns();
                if (sh == 0 && w > w1 && w <= wf && now - tlast > thd) { sh = delta; sts_vol(shw, delta); }
                const uint32_t fade = w < wf ? 256u : (uint32_t)(NU - 1 - w) * fstep;
                while ((int)(now - tnext - (sh * fade >> 8)) < 0) { __nanosleep(20); sh = __shfl_sync(~0u, lds_vol(shw), 0); now = now_ns(); }
                tlast = now;
                tnext += w >= w3 ? tau3 : w >= w2 ? tau2 : tau1;
            }
#pragma unroll
            for (int i = 0; i < V; i++) stg128(yo + i * (NWR * 16), cur[i], pol);
            yo += CHB;
            w++;
            if (w < NU) {
                if (w % UPC == 0) {
                    mbar_wait(statb + (w / UPC) * 8, 0);
                    const float2 v = ab[w / UPC]; A = v.x; B = v.y;
                    yo += (size_t)(GRID - 1) * UPC * CHB;
                }
#pragma unroll
                for (int i = 0; i < V; i++) nxt[i] = normalise(nxt[i], A, B);
            }
        };
#pragma unroll
        for (int j = 0; j < UPC; j++) fetch(R[j]);
        mbar_wait(statb, 0);
        { const float2 v = ab[0]; A = v.x; B = v.y; }
#pragma unroll
        for (int i = 0; i < V; i++) R[0][i] = normalise(R[0][i], A, B);
#define INORM_STEP(J) { \
            step(R[J], R[((J) + 1) % RD]); \
            if ((J) == (NU - 1) % RD && w == NU) break; \
            if ((J) < RD - UPC && w <= RD - UPC) { fetch(R[(UPC + 2 * (J)) % RD]); fetch(R[(UPC + 2 * (J) + 1) % RD]); } \
            else if (w + RD <= NU) fetch(R[J]); }
        static_assert(RD == 13, "unrolled below");
#pragma unroll 1
        while (true) {
            INORM_STEP(0) INORM_STEP(1) INORM_STEP(2) INORM_STEP(3) INORM_STEP(4) INORM_STEP(5) INORM_STEP(6)
            INORM_STEP(7) INORM_STEP(8) INORM_STEP(9) INORM_STEP(10) INORM_STEP(11) INORM_STEP(12)
        }
#undef INORM_STEP
    }
}

__global__ void __launch_bounds__(1024) instnorm_generic(const __nv_bfloat16* __restrict__ x, const __nv_bfloat16* __restrict__ g,
                                                         const __nv_bfloat16* __restrict__ b, __nv_bfloat16* __restrict__ y, int hw) {
    __shared__ float red[32];
    const __nv_bfloat16* xc = x + (size_t)blockIdx.x * hw;
    auto block_sum = [&](float v) {
        for (int o = 16; o; o >>= 1) v += __shfl_xor_sync(~0u, v, o);
        __syncthreads();
        if ((threadIdx.x & 31) == 0) red[threadIdx.x >> 5] = v;
        __syncthreads();
        v = red[threadIdx.x & 31];
        for (int o = 16; o; o >>= 1) v += __shfl_xor_sync(~0u, v, o);
        return v;
    };
    float s = 0.f;
    for (int i = threadIdx.x; i < hw; i += 1024) s += __bfloat162float(xc[i]);
    const float m = block_sum(s) / hw;
    float q = 0.f;
    for (int i = threadIdx.x; i < hw; i += 1024) { float d = __bfloat162float(xc[i]) - m; q += d * d; }
    const float A = __bfloat162float(g[blockIdx.x]) * rsqrtf(block_sum(q) / hw + 1e-5f), B = __bfloat162float(b[blockIdx.x]);
    for (int i = threadIdx.x; i < hw; i += 1024) y[(size_t)blockIdx.x * hw + i] = __float2bfloat16((__bfloat162float(xc[i]) - m) * A + B);
}

struct Params {
    int F = 4;
    int pace[16] = {7, 11, 14, 16, 18, 21, 24, 26, 29, 31, 33, 35, 37, 37, 37, 37};
    int w1 = 12, pf_unit = 38;
    float pf_u0 = 11.5f, pf_u1 = 38.f;
    float n0 = 16.1f, thr = .54f;
    float T1 = 25.63f, tau1 = 0.639f; int w2 = 36; float tau2 = 0.543f; int w3 = 40; float tau3 = 0.543f;
    float Tl = -0.61f, taul = 0.6343f;
    float delta = 1.37f, thd = 0.70f; int wf = 33;
    float dl = 3.16f, dl_early = 1.08f, dl_mid = 0.26f, dl_late = 1.83f;
};

inline Sched make_sched(const Params& p) {
    auto imin = [](int a, int b) { return a < b ? a : b; };
    auto imax = [](int a, int b) { return a > b ? a : b; };
    auto fetched_before = [&](int w) { return imin(NU, imin(RD + w, UPC + 2 * w)); };
    Sched s; memset(&s, 0, sizeof s);
    int need[NU];
    const int tot = (NU - p.pf_unit) * 8;
    for (int u = 0; u <= NU; u++) {
        const int pf = u <= p.pf_u0 ? 0 : u >= p.pf_u1 ? tot : (int)(tot * (u - p.pf_u0) / (p.pf_u1 - p.pf_u0));
        s.ld[u] = (uint32_t)pf << 24;
        if (u == NU) break;
        need[u] = imax(0, u - NS + 1);
        if (u >= p.pf_unit) need[u] = imax(need[u], imin(u - 1, fetched_before(imin(NU - 1, (int)(p.n0 + (u - p.pf_unit) * p.thr)))));
        const float t = p.Tl + (u + pf / 8.0f) * p.taul;
        s.ld[u] |= (uint32_t)need[u] << 16 | (u < p.pf_unit ? (uint32_t)imax(0, (int)(1000 * t)) : 0u);
        const float dl = t + p.dl + (u > 30 ? p.dl_late : u > 20 ? p.dl_mid : u >= 2 && u < p.F ? p.dl_early : 0.f);
        s.wr[u] = (u < p.pf_unit - 1 ? (uint32_t)(1000 * dl) : 0xffffu) << 16;
    }
    for (int w = 0; w < p.w1; w++) {
        int a = imin(NU - 1, p.pace[w]);
        while (a >= 0 && need[a] > fetched_before(w)) a--;
        s.wr[w] |= (uint32_t)(a + 1);
    }
    s.F = p.F; s.pf_unit = p.pf_unit; s.w1 = p.w1; s.w2 = p.w2; s.w3 = p.w3; s.wf = p.wf;
    s.T1 = (uint32_t)(1000 * p.T1 + .5f); s.tau1 = (uint32_t)(1000 * p.tau1 + .5f); s.tau2 = (uint32_t)(1000 * p.tau2 + .5f);
    s.tau3 = (uint32_t)(1000 * p.tau3 + .5f); s.delta = (uint32_t)(1000 * p.delta + .5f); s.thd = (uint32_t)(1000 * p.thd + .5f);
    return s;
}

}

extern "C" void kernel_launch(void* const* d_in, const int* in_sizes, int n_in, void* d_out, int out_size) {
    using namespace inorm;
    const __nv_bfloat16* x = (const __nv_bfloat16*)d_in[0];
    const __nv_bfloat16* g = (const __nv_bfloat16*)d_in[1];
    const __nv_bfloat16* b = (const __nv_bfloat16*)d_in[2];
    const int C = in_sizes[1];
    if (C == GRID * NCH && in_sizes[0] == C * HW) {
        cudaFuncSetAttribute(instnorm_kernel, cudaFuncAttributeMaxDynamicSharedMemorySize, SMEM);
        instnorm_kernel<<<GRID, THREADS, SMEM>>>((const char*)x, g, b, (char*)d_out, make_sched(Params()));
    } else {
        instnorm_generic<<<C, 1024>>>(x, g, b, (__nv_bfloat16*)d_out, in_sizes[0] / C);
    }
}
```

```cpp
#include <cuda_runtime.h>
#include <cuda_bf16.h>
#include <stdint.h>
#include <string.h>

namespace inorm {

constexpr int HW = 65536;
constexpr int CHB = 16384;
constexpr int UPC = HW * 2 / CHB;
constexpr int NCHAN = 640;
constexpr int GRID = 128;
constexpr int NU = NCHAN * UPC / GRID;
constexpr int NS = 14;
constexpr int RD = 13;
constexpr int PRE = 5;
constexpr int PCB = 4096;
constexpr int NP = CHB / PCB;
constexpr int NWR = 256;
constexpr int V = CHB / 16 / NWR;
constexpr int NSW = 2;
constexpr int NB = NU / 4 + 1;
constexpr int THREADS = 128 + NWR;
constexpr int SMEM = NS * CHB + 2048;
constexpr int SPIN_LIMIT = 1 << 22;
static_assert(UPC == 8 && NU == 40 && V == 4 && (2 * NS + 2 * NB) * 8 <= 416, "lane mappings and shared-memory layout below");

struct Sched {
    uint32_t ld[NU + 1];
    uint32_t st[NU];
    uint16_t dl[NU];
    uint32_t ldstep;
    int F0, F;
    int pf_unit;
    uint32_t tg0, tg1, lead2, lead, leadl;
    int w1;
    uint32_t delta, delta2;
    uint32_t thd;
    int wf;
};

__device__ __forceinline__ uint32_t smem_u32(const void* p) { return (uint32_t)__cvta_generic_to_shared(p); }
__device__ __forceinline__ void mbar_init(uint32_t bar, uint32_t cnt) { asm volatile("mbarrier.init.shared::cta.b64 [%0], %1;" :: "r"(bar), "r"(cnt) : "memory"); }
__device__ __forceinline__ void mbar_expect_tx(uint32_t bar, uint32_t bytes) { asm volatile("mbarrier.arrive.expect_tx.shared::cta.b64 _, [%0], %1;" :: "r"(bar), "r"(bytes) : "memory"); }
__device__ __forceinline__ void mbar_arrive(uint32_t bar) { asm volatile("mbarrier.arrive.shared::cta.b64 _, [%0];" :: "r"(bar) : "memory"); }
__device__ __forceinline__ bool mbar_try(uint32_t bar, uint32_t parity) {
    uint32_t ok;
    asm volatile("{\n.reg .pred p;\nmbarrier.try_wait.parity.shared::cta.b64 p, [%1], %2;\nselp.u32 %0, 1, 0, p;\n}" : "=r"(ok) : "r"(bar), "r"(parity) : "memory");
    return ok;
}
__device__ __forceinline__ bool mbar_test(uint32_t bar, uint32_t parity) {
    uint32_t ok;
    asm volatile("{\n.reg .pred p;\nmbarrier.test_wait.parity.shared::cta.b64 p, [%1], %2;\nselp.u32 %0, 1, 0, p;\n}" : "=r"(ok) : "r"(bar), "r"(parity) : "memory");
    return ok;
}
__device__ __forceinline__ void mbar_wait(uint32_t bar, uint32_t parity) {
    int it = 0;
#pragma unroll 1
    while (!mbar_try(bar, parity)) { if (++it > SPIN_LIMIT) break; }
}
__host__ __device__ constexpr uint32_t goff(uint32_t o) { return o / PCB * (UPC * PCB) + o % PCB; }
__device__ __forceinline__ void bulk_load(uint32_t dst, const char* src, uint32_t bar, uint64_t pol) {
    mbar_expect_tx(bar, CHB);
#pragma unroll
    for (int i = 0; i < NP; i++)
        asm volatile("cp.async.bulk.shared::cluster.global.mbarrier::complete_tx::bytes.L2::cache_hint [%0], [%1], %2, [%3], %4;"
                     :: "r"(dst + i * PCB), "l"(src + goff(i * PCB)), "n"(PCB), "r"(bar), "l"(pol) : "memory");
}
__device__ __forceinline__ void bulk_prefetch(const void* src, uint32_t bytes) {
    asm volatile("cp.async.bulk.prefetch.L2.global [%0], %1;" :: "l"(src), "r"(bytes) : "memory");
}
__device__ __forceinline__ uint64_t policy_evict_first() { uint64_t p; asm volatile("createpolicy.fractional.L2::evict_first.b64 %0, 1.0;" : "=l"(p)); return p; }
__device__ __forceinline__ uint4 lds128(uint32_t a) {
    uint4 v; asm volatile("ld.shared.v4.u32 {%0,%1,%2,%3}, [%4];" : "=r"(v.x), "=r"(v.y), "=r"(v.z), "=r"(v.w) : "r"(a) : "memory"); return v;
}
__device__ __forceinline__ uint32_t lds_vol(uint32_t a) { uint32_t v; asm volatile("ld.volatile.shared.u32 %0, [%1];" : "=r"(v) : "r"(a) : "memory"); return v; }
__device__ __forceinline__ float2 lds_f2(uint32_t a) { float2 v; asm volatile("ld.volatile.shared.v2.f32 {%0, %1}, [%2];" : "=f"(v.x), "=f"(v.y) : "r"(a) : "memory"); return v; }
__device__ __forceinline__ void sts_vol(uint32_t a, uint32_t v) { asm volatile("st.volatile.shared.u32 [%0], %1;" :: "r"(a), "r"(v) : "memory"); }
__device__ __forceinline__ void stg128(void* p, uint4 v, uint64_t pol) {
    asm volatile("st.global.L2::cache_hint.v4.u32 [%0], {%1,%2,%3,%4}, %5;" :: "l"(p), "r"(v.x), "r"(v.y), "r"(v.z), "r"(v.w), "l"(pol) : "memory");
}
__device__ __forceinline__ uint32_t now_ns() { uint32_t t; asm volatile("mov.u32 %0, %globaltimer_lo;" : "=r"(t)); return t; }
__device__ __forceinline__ bool elect_one() { uint32_t p; asm volatile("{\n.reg .pred p;\nelect.sync _|p, 0xffffffff;\nselp.u32 %0, 1, 0, p;\n}" : "=r"(p)); return p; }
__device__ __forceinline__ float bf_lo(uint32_t u) { return __uint_as_float(u << 16); }
__device__ __forceinline__ float bf_hi(uint32_t u) { return __uint_as_float(u & 0xffff0000u); }
__device__ __forceinline__ uint32_t pack_bf(float lo, float hi) { uint32_t r; asm("cvt.rn.bf16x2.f32 %0, %1, %2;" : "=r"(r) : "f"(hi), "f"(lo)); return r; }
__device__ __forceinline__ uint32_t sub_bf2(uint32_t a, uint32_t b) { uint32_t r; asm("sub.rn.bf16x2 %0, %1, %2;" : "=r"(r) : "r"(a), "r"(b)); return r; }
__device__ __forceinline__ void mma_k16(float (&d)[4], uint32_t a0, uint32_t a1, uint32_t a2, uint32_t a3, uint32_t b0, uint32_t b1) {
    asm("mma.sync.aligned.m16n8k16.row.col.f32.bf16.bf16.f32 {%0,%1,%2,%3}, {%4,%5,%6,%7}, {%8,%9}, {%0,%1,%2,%3};"
        : "+f"(d[0]), "+f"(d[1]), "+f"(d[2]), "+f"(d[3]) : "r"(a0), "r"(a1), "r"(a2), "r"(a3), "r"(b0), "r"(b1));
}
__device__ __forceinline__ void mma_rowsum(float (&d)[4], uint32_t a0, uint32_t a1, uint32_t a2, uint32_t a3) {
    asm("mma.sync.aligned.m16n8k16.row.col.f32.bf16.bf16.f32 {%0,%1,%2,%3}, {%4,%5,%6,%7}, {%8,%8}, {%0,%1,%2,%3};"
        : "+f"(d[0]), "+f"(d[1]), "+f"(d[2]), "+f"(d[3]) : "r"(a0), "r"(a1), "r"(a2), "r"(a3), "r"(0x3f803f80u));
}
__device__ __forceinline__ void accumulate(uint4 v, uint32_t K2, float (&S)[4], float (&Q0)[4], float (&Q1)[4]) {
    uint32_t d0 = sub_bf2(v.x, K2), d1 = sub_bf2(v.y, K2), d2 = sub_bf2(v.z, K2), d3 = sub_bf2(v.w, K2);
    mma_k16(Q0, d0, d2, d1, d3, v.x, v.y);
    mma_k16(Q1, d0, d2, d1, d3, v.z, v.w);
    mma_rowsum(S, d0, d2, d1, d3);
}
__device__ __forceinline__ uint4 normalise(uint4 v, float A, float B) {
    return make_uint4(pack_bf(fmaf(bf_lo(v.x), A, B), fmaf(bf_hi(v.x), A, B)), pack_bf(fmaf(bf_lo(v.y), A, B), fmaf(bf_hi(v.y), A, B)),
                      pack_bf(fmaf(bf_lo(v.z), A, B), fmaf(bf_hi(v.z), A, B)), pack_bf(fmaf(bf_lo(v.w), A, B), fmaf(bf_hi(v.w), A, B)));
}

__device__ __align__(256) ulonglong2 g_xch[NCHAN * UPC * 2];
__device__ __align__(256) uint32_t g_epoch[GRID * 8];
__device__ __forceinline__ uint32_t ld_relaxed(const uint32_t* p) { uint32_t v; asm volatile("ld.relaxed.gpu.global.u32 %0, [%1];" : "=r"(v) : "l"(p) : "memory"); return v; }
__device__ __forceinline__ void xch_store(ulonglong2* p, float m, float q, uint32_t tag) {
    asm volatile("{\n.reg .b64 a, b;\nmov.b64 a, {%1, %3};\nmov.b64 b, {%2, %3};\nst.relaxed.gpu.global.v2.b64 [%0], {a, b};\n}" :: "l"(p), "f"(m), "f"(q), "r"(tag) : "memory");
}
__device__ __forceinline__ bool xch_load(const ulonglong2* p, float& m, float& q, uint32_t tag) {
    uint32_t t0, t1;
    asm volatile("{\n.reg .b64 a, b;\nld.relaxed.gpu.global.v2.b64 {a, b}, [%4];\nmov.b64 {%0, %2}, a;\nmov.b64 {%1, %3}, b;\n}" : "=f"(m), "=f"(q), "=r"(t0), "=r"(t1) : "l"(p) : "memory");
    return t0 == tag && t1 == tag;
}

__global__ void __launch_bounds__(THREADS, 1)
instnorm_kernel(const char* __restrict__ x, const __nv_bfloat16* __restrict__ g, const __nv_bfloat16* __restrict__ b,
                char* __restrict__ y, ulonglong2* __restrict__ xch, uint32_t* __restrict__ epoch, const __grid_constant__ Sched sc) {
    extern __shared__ __align__(128) char smem[];
    const uint32_t ring = smem_u32(smem);
    const uint32_t full = ring + NS * CHB, empty = full + NS * 8, pubb = empty + NS * 8, statb = pubb + NB * 8;
    float2* ab = (float2*)(smem + NS * CHB + 416);
    const uint32_t shw = ring + NS * CHB + 1016;
    uint32_t* wtab = (uint32_t*)(smem + NS * CHB + 1024);
    uint32_t* ltab = wtab + NU + 1;
    uint32_t* dtab = ltab + NU + 1;
    float2* gb = (float2*)(smem + NS * CHB + 1536);
    const uint32_t grp = (blockIdx.x / UPC * 9) % (GRID / UPC), part = blockIdx.x % UPC;
    constexpr size_t USTR = (size_t)GRID * CHB;
    const uint32_t boff = grp * (UPC * CHB) + part * PCB;
    const char* xb = x + boff;
    if (threadIdx.x - 32 < 64) asm volatile("prefetch.global.L2 [%0];" :: "l"(xb + goff((threadIdx.x - 32) * 128)));
    uint32_t tag = 0;
    if (threadIdx.x >> 5 == 1) tag = ld_relaxed(epoch + blockIdx.x * 8);
    const uint64_t pol = policy_evict_first();
    if (threadIdx.x == 0) {
        mbar_init(full, 1);
        bulk_load(ring, xb, full, pol);
        sts_vol(shw + 4, now_ns());
        mbar_init(full + 8, 1);
        bulk_load(ring + CHB, xb + USTR, full + 8, pol);
#pragma unroll
        for (int s = 2; s < NS; s++) mbar_init(full + s * 8, 1);
        for (int u = 2; u < sc.F0; u++) bulk_load(ring + u * CHB, xb + u * USTR, full + u * 8, pol);
#pragma unroll
        for (int s = 0; s < NS; s++) mbar_init(empty + s * 8, NWR / 32 + 1);
        asm volatile("fence.mbarrier_init.release.cluster;" ::: "memory");
    }
    if (threadIdx.x == 96) {
#pragma unroll
        for (int s = 0; s < NB; s++) { mbar_init(pubb + s * 8, s < 2 ? 2 : 4); mbar_init(statb + s * 8, 1); }
    }
    if (threadIdx.x >= 128 && threadIdx.x <= 128 + NU) {
        int i = threadIdx.x - 128;
        ltab[i] = sc.ld[i] + grp * sc.ldstep;
        if (i < NU) {
            const uint32_t e = sc.st[i];
            wtab[i] = (e & 0xff00ffffu) + grp * ((e >> 16) & 0xff);
            dtab[i] = sc.dl[i] + grp * sc.ldstep;
        } else { wtab[i] = 0; sts_vol(shw, 0); sts_vol(shw - 4, 0); }
    }
    const int wid = __shfl_sync(~0u, threadIdx.x >> 5, 0);
    const int lane = threadIdx.x & 31;
    __syncthreads();
    const uint32_t tstart = __shfl_sync(~0u, lds_vol(shw + 4), 0);

    if (wid < 4) {
        asm volatile("setmaxnreg.dec.sync.aligned.u32 40;");
        if ((wid & 3) == 0) {
            if (lane == 0) {
                const int F = sc.F;
                const char* pfb = xb + sc.pf_unit * USTR;
                uint32_t sh = 0;
                int rel = 0, rs = 0, rp = 0;
                int arr = 0, as = 0, ap = 0;
                uint32_t dl = dtab[0];
                int s = sc.F0;
                for (int u = s; u < NU; u++) {
                    const uint32_t e = ltab[u], e1 = ltab[u + 1];
                    const int need = (e >> 16) & 0xff;
#pragma unroll 1
                    for (int it = 0; it < SPIN_LIMIT; it++) {
                        const uint32_t t = now_ns() - tstart;
                        if (arr > u - F && rel >= need && t >= (e & 0xffff) + sh) break;
                        if (arr < u) {
                            if (mbar_test(full + as * 8, ap)) { arr++; dl = dtab[arr]; if (++as == NS) { as = 0; ap ^= 1; } }
                            else if (t > dl && sh == 0) { sh = sc.delta; if (lds_vol(shw) == 0) sts_vol(shw, sh); }
                        }
                        if (rel < need && mbar_test(empty + rs * 8, rp)) { rel++; if (++rs == NS) { rs = 0; rp ^= 1; } }
                    }
                    bulk_load(ring + s * CHB, xb + u * USTR, full + s * 8, pol);
                    if (++s == NS) s = 0;
#pragma unroll 1
                    for (uint32_t q = e >> 24; q < e1 >> 24; q++) bulk_prefetch(pfb + (q >> 3) * USTR + goff((q & 7) * (CHB / 8)), CHB / 8);
                }
            }
        } else if ((wid & 2) == 0) {
            tag = tag + 1 ? tag + 1 : 1;
            sts_vol(shw - 4, tag);
            for (int i = lane; i < NU; i += 32) {
                const int c = i * (GRID / UPC) + grp;
                gb[i] = make_float2(__bfloat162float(g[c]), __bfloat162float(b[c]));
            }
            __syncwarp();
            const ulonglong2* src = xch + ((blockIdx.x & ~(UPC - 1)) + (lane & 7)) * 2;
            const uint32_t tgl = lane < 2 ? (lane ? sc.tg1 : sc.tg0) + grp * sc.ldstep
                               : lane < NB ? (wtab[4 * lane - 5] & 0xffffff) - (lane == 2 ? sc.lead2 : lane == NB - 1 ? sc.leadl : sc.lead) : 0;
#pragma unroll 1
            for (int j = 0; j < NB; j++) {
                const int u = j < 2 ? 2 * j + ((lane >> 3) & 1) : 4 * j - 4 + (lane >> 3);
                mbar_wait(pubb + j * 8, 0);
                const uint32_t tg = __shfl_sync(~0u, tgl, j);
#pragma unroll 1
                for (int it = 0; it < SPIN_LIMIT && now_ns() - tstart < tg + lds_vol(shw); it++) __nanosleep(50);
                float mu = 0.f, qu = 0.f;
#pragma unroll 1
                for (int it = 0; it < SPIN_LIMIT; it++) {
                    const bool ok = xch_load(src + u * (GRID * 2), mu, qu, tag);
                    if (__all_sync(~0u, ok)) break;
                    __nanosleep(500);
                }
                float m = mu;
#pragma unroll
                for (int o = 1; o < 8; o <<= 1) m += __shfl_xor_sync(~0u, m, o);
                m *= 0.125f;
                float q = qu + (float)(HW / UPC) * (mu - m) * (mu - m);
#pragma unroll
                for (int o = 1; o < 8; o <<= 1) q += __shfl_xor_sync(~0u, q, o);
                float var = q * (1.0f / HW);
                var = var < 0.f ? 0.f : var;
                const float mb = bf_lo(pack_bf(m, 0.f));
                var += (m - mb) * (m - mb);
                const float2 gv = gb[u];
                const float A = gv.x * rsqrtf(var + 1e-5f);
                if ((lane & 7) == 0) ab[u] = make_float2(A, gv.y - mb * A);
                __syncwarp();
                if (elect_one()) mbar_arrive(statb + j * 8);
            }
            if (lane == 0) epoch[blockIdx.x * 8] = tag;
        } else {
            const int sw = wid - 2;
            const bool diag = (lane & 3) == (lane >> 3), odd = (lane >> 2) & 1;
            uint32_t s = sw, p = 0;
#pragma unroll 1
            for (int jj = 0; jj < NU / NSW; jj++) {
                const int u = jj * NSW + sw;
                mbar_wait(full + s * 8, p);
                uint32_t a = ring + s * CHB + lane * 16;
                uint4 v0 = lds128(a), v1 = lds128(a + 512);
                float S[4] = {0, 0, 0, 0}, Q0[4] = {0, 0, 0, 0}, Q1[4] = {0, 0, 0, 0};
                mma_rowsum(S, v0.x, v0.y, v0.z, v0.w);
                const float kk = (S[0] + S[2]) * (1.0f / 32.0f);
                const uint32_t K2 = pack_bf(kk, kk);
                S[0] = S[1] = S[2] = S[3] = 0.f;
#pragma unroll 1
                for (int r = 0; r < 15; r++) {
                    a += 1024;
                    accumulate(v0, K2, S, Q0, Q1);
                    v0 = lds128(a);
                    accumulate(v1, K2, S, Q0, Q1);
                    v1 = lds128(a + 512);
                }
                __syncwarp();
                if (elect_one()) mbar_arrive(empty + s * 8);
                accumulate(v0, K2, S, Q0, Q1);
                accumulate(v1, K2, S, Q0, Q1);
                constexpr float NG = HW / UPC / 8;
                const float sg = S[0] + S[2];
                const float mg = bf_lo(K2) + sg * (1.0f / NG);
                float m = mg;
#pragma unroll
                for (int o = 4; o < 32; o <<= 1) m += __shfl_xor_sync(~0u, m, o);
                m *= 0.125f;
                float q = odd ? Q0[1] + Q1[3] : Q0[0] + Q1[2];
                q = diag ? (q - sg * mg) + NG * (mg - m) * (mg - m) : 0.f;
#pragma unroll
                for (int o = 1; o < 32; o <<= 1) q += __shfl_xor_sync(~0u, q, o);
                uint32_t tg = lds_vol(shw - 4);
#pragma unroll 1
                for (int it = 0; it < SPIN_LIMIT && tg == 0; it++) tg = lds_vol(shw - 4);
                if (lane < 2) xch_store(xch + (u * GRID + blockIdx.x) * 2 + lane, m, q, tg);
                if (lane == 0) mbar_arrive(pubb + (u < 2 ? 0 : (u >> 2) + 1) * 8);
                s += NSW;
                if (s >= NS) { s -= NS; p ^= 1; }
            }
        }
    } else {
        asm volatile("setmaxnreg.inc.sync.aligned.u32 232;");
        const int tid = threadIdx.x - 128;
        const int w1 = sc.w1, wf = sc.wf;
        const uint32_t delta = sc.delta2, thd = sc.thd, fstep = 256 / (NU - sc.wf);
        uint32_t tlast = 0;
        uint4 R[RD][V];
        uint32_t cs = 0;
        int fu = 0;
        int known = 0; uint32_t ks = 0, kp = 0;
        int w = 0;
        constexpr int IST = 512;
        const uint32_t toff = (tid >> 5) * (V * IST) + lane * 16;
        const uint32_t ta = ring + toff;
        char* yo = y + boff + goff(toff);
        auto learn = [&](int n) { while (known < n) { mbar_wait(full + ks * 8, kp); known++; if (++ks == NS) { ks = 0; kp ^= 1; } } };
        auto fetch = [&](uint4 (&dst)[V]) {
            learn(++fu);
            const uint32_t a = ta + cs * CHB;
#pragma unroll
            for (int i = 0; i < V; i++) dst[i] = lds128(a + i * IST);
            __syncwarp();
            if (elect_one()) mbar_arrive(empty + cs * 8);
            if (++cs == NS) cs = 0;
        };
        auto step = [&](uint4 (&cur)[V], uint4 (&nxt)[V]) {
            const uint32_t e = __shfl_sync(~0u, lds_vol(smem_u32(wtab) + w * 4), 0);
            uint32_t sh = __shfl_sync(~0u, lds_vol(shw), 0);
            uint32_t now = now_ns() - tstart;
            if (sh == 0 && w > w1 && w <= wf && now - tlast > thd) { sh = delta; sts_vol(shw, delta); }
            learn(e >> 24);
            const uint32_t fade = w < wf ? 256u : (uint32_t)(NU - 1 - w) * fstep;
#pragma unroll 1
            for (int it = 0; it < SPIN_LIMIT && now < (e & 0xffffff) + (sh * fade >> 8); it++) {
                __nanosleep(20);
                sh = __shfl_sync(~0u, lds_vol(shw), 0);
                now = now_ns() - tstart;
            }
            tlast = now;
            w++;
            float2 v = lds_f2(smem_u32(ab) + w * 8);
#pragma unroll
            for (int i = 0; i < V; i++) stg128(yo + i * IST, cur[i], pol);
            yo += USTR;
            if (((w & 3) == 0 && w < NU) || w == 2) { mbar_wait(statb + ((w >> 2) + 1) * 8, 0); v = lds_f2(smem_u32(ab) + w * 8); }
            if (w < NU) {
#pragma unroll
                for (int i = 0; i < V; i++) nxt[i] = normalise(nxt[i], v.x, v.y);
            }
        };
#pragma unroll
        for (int j = 0; j < PRE; j++) fetch(R[j]);
        mbar_wait(statb, 0);
        {
            const float2 v = ab[0];
#pragma unroll
            for (int i = 0; i < V; i++) R[0][i] = normalise(R[0][i], v.x, v.y);
        }
#define INORM_STEP(J) { \
            step(R[(J) % RD], R[((J) + 1) % RD]); \
            if ((J) == (NU - 1) % RD && w == NU) break; \
            if ((J) < RD - PRE && w <= RD - PRE) { fetch(R[(PRE + 2 * (J)) % RD]); fetch(R[(PRE + 2 * (J) + 1) % RD]); } \
            else if (w + RD <= NU) fetch(R[(J) % RD]); }
        static_assert(RD == 13, "unrolled below");
#pragma unroll 1
        while (true) {
            INORM_STEP(0) INORM_STEP(1) INORM_STEP(2) INORM_STEP(3) INORM_STEP(4) INORM_STEP(5) INORM_STEP(6)
            INORM_STEP(7) INORM_STEP(8) INORM_STEP(9) INORM_STEP(10) INORM_STEP(11) INORM_STEP(12)
        }
#undef INORM_STEP
    }
}

__global__ void __launch_bounds__(1024) instnorm_generic(const __nv_bfloat16* __restrict__ x, const __nv_bfloat16* __restrict__ g,
                                                         const __nv_bfloat16* __restrict__ b, __nv_bfloat16* __restrict__ y, int hw) {
    __shared__ float red[32];
    const __nv_bfloat16* xc = x + (size_t)blockIdx.x * hw;
    auto block_sum = [&](float v) {
        for (int o = 16; o; o >>= 1) v += __shfl_xor_sync(~0u, v, o);
        __syncthreads();
        if ((threadIdx.x & 31) == 0) red[threadIdx.x >> 5] = v;
        __syncthreads();
        v = red[threadIdx.x & 31];
        for (int o = 16; o; o >>= 1) v += __shfl_xor_sync(~0u, v, o);
        return v;
    };
    float s = 0.f;
    for (int i = threadIdx.x; i < hw; i += 1024) s += __bfloat162float(xc[i]);
    const float m = __bfloat162float(__float2bfloat16(block_sum(s) / hw));
    float q = 0.f;
    for (int i = threadIdx.x; i < hw; i += 1024) { float d = __bfloat162float(xc[i]) - m; q += d * d; }
    const float A = __bfloat162float(g[blockIdx.x]) * rsqrtf(block_sum(q) / hw + 1e-5f), B = __bfloat162float(b[blockIdx.x]);
    for (int i = threadIdx.x; i < hw; i += 1024) y[(size_t)blockIdx.x * hw + i] = __float2bfloat16((__bfloat162float(xc[i]) - m) * A + B);
}

struct Params {
    int F0 = 2, F = 4;
    int w1 = 11, pf_unit = 38;
    float pf_u0 = 7.f, pf_u1 = 38.f;
    float n0 = 17.6f, thr = 4.5f;
    float Ta = 4.5f, T1 = 24.42f;
    float tau1 = 0.627f; int w2 = 35; float tau2 = 0.54f; int w3 = 38; float tau3 = 0.33f;
    float alpha = 1.f, beta = 1.f;
    float Tl = -0.71f, taul = 0.6375f, stagl = 0.04f;
    float back = 2.5f;
    float delta = 1.45f, delta2 = 1.8f, thd = 0.7f; int wf = 36;
    float dl_early = 3.f, dl = 2.68f, dl_knee = 32.5f, dl_slope = 0.35f;
    float tg0 = 3.5f, tg1 = 5.9f, lead2 = 1.4f, lead = 3.2f, leadl = 2.2f;
};

inline Sched make_sched(const Params& p) {
    auto imin = [](int a, int b) { return a < b ? a : b; };
    auto imax = [](int a, int b) { return a > b ? a : b; };
    auto ns = [](float t) { return (uint32_t)(t > 0.f ? 1000.f * t + .5f : 0.f); };
    auto fetched_before = [&](int w) { return imin(NU, imin(RD + w, PRE + 2 * w)); };
    Sched s; memset(&s, 0, sizeof s);
    int need[NU];
    float tl[NU], tw[NU + 1];
    const int tot = (NU - p.pf_unit) * 8;
    for (int u = 0; u <= NU; u++) {
        const int pf = u <= p.pf_u0 ? 0 : u >= p.pf_u1 ? tot : (int)(tot * (u - p.pf_u0) / (p.pf_u1 - p.pf_u0));
        s.ld[u] = (uint32_t)pf << 24;
        if (u == NU) break;
        need[u] = imax(0, u - NS + 1);
        if (u >= p.pf_unit) need[u] = imax(need[u], imin(u - 1, fetched_before(imin(NU - 1, (int)(p.n0 + (u - p.pf_unit) * p.thr)))));
        tl[u] = p.Tl + (u + pf / 8.0f) * p.taul;
        s.ld[u] |= (uint32_t)need[u] << 16 | (u < p.pf_unit ? ns(tl[u]) : 0u);
        const float dl = u < 6 ? p.dl_early : p.dl + (u > p.dl_knee ? (u - p.dl_knee) * p.dl_slope : 0.f);
        s.dl[u] = u >= 2 && u < p.pf_unit ? ns(tl[u] + dl) : 0xffffu;
    }
    for (int w = 0; w <= NU; w++)
        tw[w] = w <= p.w1 ? p.Ta + (p.T1 - p.Ta) * w / p.w1 : tw[w - 1] + (w > p.w3 ? p.tau3 : w > p.w2 ? p.tau2 : p.tau1);
    for (int w = 0; w < NU; w++) {
        int a = 0;
        if (w <= p.w1) while (a < p.pf_unit && tl[a] < tw[w] - p.back && need[a] <= fetched_before(w)) a++;
        s.st[w] = ns(tw[w]) | ns((tw[w + 1] - tw[w]) * (w < p.w1 ? p.alpha : p.beta) / (GRID / UPC)) << 16 | (uint32_t)a << 24;
    }
    s.ldstep = ns(p.stagl);
    s.F0 = p.F0; s.F = p.F; s.pf_unit = p.pf_unit; s.w1 = p.w1; s.wf = p.wf;
    s.delta = ns(p.delta); s.delta2 = ns(p.delta2); s.thd = ns(p.thd);
    s.tg0 = ns(p.tg0); s.tg1 = ns(p.tg1); s.lead2 = ns(p.lead2); s.lead = ns(p.lead); s.leadl = ns(p.leadl);
    return s;
}

inline void launch(const void* x, const __nv_bfloat16* g, const __nv_bfloat16* b, void* y, const Params& p, cudaStream_t st) {
    void *xch, *epoch;
    cudaGetSymbolAddress(&xch, g_xch);
    cudaGetSymbolAddress(&epoch, g_epoch);
    cudaFuncSetAttribute(instnorm_kernel, cudaFuncAttributeMaxDynamicSharedMemorySize, SMEM);
    instnorm_kernel<<<GRID, THREADS, SMEM, st>>>((const char*)x, g, b, (char*)y, (ulonglong2*)xch, (uint32_t*)epoch, make_sched(p));
}

}

extern "C" void kernel_launch(void* const* d_in, const int* in_sizes, int n_in, void* d_out, int out_size) {
    using namespace inorm;
    const __nv_bfloat16* x = (const __nv_bfloat16*)d_in[0];
    const __nv_bfloat16* g = (const __nv_bfloat16*)d_in[1];
    const __nv_bfloat16* b = (const __nv_bfloat16*)d_in[2];
    const int C = in_sizes[1];
    if (C == NCHAN && in_sizes[0] == C * HW) {
        launch(x, g, b, d_out, Params(), 0);
    } else {
        instnorm_generic<<<C, 1024>>>(x, g, b, (__nv_bfloat16*)d_out, in_sizes[0] / C);
    }
}
```
